```python
import torch

def _softmax(x, axis=-1):
    return torch.softmax(x, dim=axis)
def _gelu(x):
    return torch.nn.functional.gelu(x, approximate="tanh")
def _silu(x):
    return torch.nn.functional.silu(x)
def _sigmoid(x):
    return torch.sigmoid(x)
def _layernorm(x, axis=-1, eps=1e-5):
    m = x.mean(dim=axis, keepdim=True)
    v = x.var(dim=axis, keepdim=True, unbiased=False)
    return (x - m) / torch.sqrt(v + eps)
def _scatter_add(tgt, idx, src, axis=0):
    return tgt.clone().index_add_(axis, idx, src)
def _segment_sum(src, seg, n):
    out = torch.zeros((n,) + src.shape[1:], dtype=src.dtype)
    return out.index_add_(0, seg, src)
def _pad(x, pw):
    flat = tuple(v for pair in reversed(pw) for v in pair)
    return torch.nn.functional.pad(x, flat)

kernel_name = 'standalone__gqa_block_cached__near_ridge'

def setup_inputs():

    _w = (lambda a: (lambda t: t.to(torch.bfloat16) if t.is_floating_point() else t)(torch.as_tensor(a)))
    B, Sq, D = 8, 48, 1024
    Hq, Hkv, Sk, Dh = 32, 4, 2048, 128
    assert Hq % Hkv == 0, (Hq, Hkv)
    return {
        "x": _w((lambda *s: torch.randn(*s, dtype=torch.bfloat16) * 0.8)(B, Sq, D)),
        "k_cache": _w((lambda *s: torch.randn(*s, dtype=torch.bfloat16) * 0.8)(B, Hkv, Sk, Dh)),
        "v_cache": _w((lambda *s: torch.randn(*s, dtype=torch.bfloat16) * 0.05)(B, Hkv, Sk, Dh)),
        "wq": _w((lambda *s: torch.randn(*s, dtype=torch.bfloat16) * 0.8)(D, Hq * Dh) * (D ** -0.5)),
        "wo": _w((lambda *s: torch.randn(*s, dtype=torch.bfloat16) * 0.05)(Hq * Dh, D) * ((Hq * Dh) ** -0.5)),
    }

def reference(x, k_cache, v_cache, wq, wo):
    B, Sq, D = x.shape
    Hq, Dh = 32, 128
    Hkv = k_cache.shape[1]
    rep = Hq // Hkv
    q = (lambda x, *d: x.permute(*d))((x @ wq).reshape(B, Sq, Hq, Dh), 0, 2, 1, 3)
    k = (lambda x, n, axis: torch.repeat_interleave(x, n, dim=axis))(k_cache, rep, axis=1)
    v = (lambda x, n, axis: torch.repeat_interleave(x, n, dim=axis))(v_cache, rep, axis=1)
    scores = torch.einsum("bhqd,bhkd->bhqk", q, k) * (Dh ** -0.5)
    p = _softmax(scores, axis=-1)
    o = torch.einsum("bhqk,bhkd->bhqd", p, v)
    return (lambda x, *d: x.permute(*d))(o, 0, 2, 1, 3).reshape(B, Sq, Hq * Dh) @ wo
```

```cpp
#include <cuda_runtime.h>
#include <cuda_bf16.h>
#include <cuda.h>
#include <stdint.h>

#define NCTA 128
#define WD 450
#define XD 550
#define PACE 1300
#define NS 3
#define KS 4
#define NTHREADS 512
#define QSCALE (0.08838834764831845f * 1.4426950408889634f)

#define SM_RING   0
#define SM_Q      163840
#define SM_ML     212992
#define SM_BAR    214528
#define SM_TOTAL  215040
#define B_FULL    0
#define B_EMPTY   6
#define B_EPOCH   12
#define B_ZOK     13
#define B_QGO     14
#define B_ML      15
#define B_XB      27
#define B_P3GO    39
#define B_COUNT   40
#define SM_EPOCHV (SM_BAR + 8 * B_COUNT)

__device__ __align__(1024) unsigned char g_qs[8 * 8 * 49152];
__device__ __align__(1024) unsigned char g_os[2 * 8 * 196608];
__device__ __align__(1024) unsigned int g_cnt[(2 + 48 + 48) * 32];
#define CNT_TICKET 0
#define CNT_ZERO (97 * 32)
#define CNT_Q(mh, hq, w) ((1 + ((mh) * 8 + (hq)) * 3 + (w)) * 32)
#define CNT_O(mh, hq, w) ((49 + ((mh) * 8 + (hq)) * 3 + (w)) * 32)

__device__ __forceinline__ uint32_t smem_u32(const void* p) { return (uint32_t)__cvta_generic_to_shared(p); }
__device__ __forceinline__ void mbar_init(uint32_t b, uint32_t c) {
    asm volatile("mbarrier.init.shared::cta.b64 [%0], %1;" ::"r"(b), "r"(c) : "memory");
}
__device__ __forceinline__ void mbar_expect_tx(uint32_t b, uint32_t bytes) {
    asm volatile("mbarrier.arrive.expect_tx.shared::cta.b64 _, [%0], %1;" ::"r"(b), "r"(bytes) : "memory");
}
__device__ __forceinline__ void mbar_arrive(uint32_t b) {
    asm volatile("mbarrier.arrive.shared::cta.b64 _, [%0];" ::"r"(b) : "memory");
}
__device__ __forceinline__ void mbar_wait(uint32_t b, uint32_t ph) {
    asm volatile("{\n.reg .pred p, q;\n.reg .u32 n;\nmov.u32 n, 0;\n"
                 "WAIT_LOOP:\nmbarrier.try_wait.parity.shared::cta.b64 p, [%0], %1;\n@p bra WAIT_DONE;\n"
                 "add.u32 n, n, 1;\nsetp.gt.u32 q, n, 0x100000;\n@q trap;\nbra WAIT_LOOP;\nWAIT_DONE:\n}"
                 ::"r"(b), "r"(ph) : "memory");
}
__device__ __forceinline__ void mbar_arrive_if(uint32_t b, uint32_t n, int pred) {
    asm volatile("{\n.reg .pred p;\nsetp.ne.s32 p, %2, 0;\n@p mbarrier.arrive.shared::cta.b64 _, [%0], %1;\n}"
                 ::"r"(b), "r"(n), "r"(pred) : "memory");
}
__device__ __forceinline__ void tma2d(uint32_t dst, const CUtensorMap* m, uint32_t bar, int c0, int c1, uint64_t pol) {
    asm volatile("cp.async.bulk.tensor.2d.shared::cluster.global.mbarrier::complete_tx::bytes.L2::cache_hint "
                 "[%0], [%1, {%3, %4}], [%2], %5;"
                 ::"r"(dst), "l"(m), "r"(bar), "r"(c0), "r"(c1), "l"(pol) : "memory");
}
__device__ __forceinline__ void tma3d_red_add(const CUtensorMap* m, uint32_t src, int c0, int c1, int c2) {
    asm volatile("cp.reduce.async.bulk.tensor.3d.global.shared::cta.add.tile.bulk_group [%0, {%2, %3, %4}], [%1];"
                 ::"l"(m), "r"(src), "r"(c0), "r"(c1), "r"(c2) : "memory");
}
__device__ __forceinline__ bool mbar_test(uint32_t b, uint32_t ph) {
    uint32_t ok;
    asm volatile("{\n.reg .pred p;\nmbarrier.test_wait.parity.shared::cta.b64 p, [%1], %2;\nselp.u32 %0, 1, 0, p;\n}"
                 : "=r"(ok) : "r"(b), "r"(ph) : "memory");
    return ok;
}
__device__ __forceinline__ uint32_t clock32() { uint32_t c; asm volatile("mov.u32 %0, %%clock;" : "=r"(c)); return c; }
__device__ __forceinline__ void bulk_commit() { asm volatile("cp.async.bulk.commit_group;" ::: "memory"); }
__device__ __forceinline__ void bulk_wait0_read() { asm volatile("cp.async.bulk.wait_group.read 0;" ::: "memory"); }
__device__ __forceinline__ void fence_async_smem() { asm volatile("fence.proxy.async.shared::cta;" ::: "memory"); }
__device__ __forceinline__ void fence_async_global() { asm volatile("fence.proxy.async.global;" ::: "memory"); }
__device__ __forceinline__ unsigned ld_acquire(const unsigned* p) {
    unsigned v;
    asm volatile("ld.acquire.gpu.global.u32 %0, [%1];" : "=r"(v) : "l"(p) : "memory");
    return v;
}
__device__ __forceinline__ void red_relaxed(unsigned* p) {
    asm volatile("red.relaxed.gpu.global.add.u32 [%0], 1;" ::"l"(p) : "memory");
}
__device__ __forceinline__ void poll_ge(const unsigned* p, unsigned target) {
    for (int n = 0;; n++) {
        unsigned v;
        asm volatile("ld.relaxed.gpu.global.u32 %0, [%1];" : "=r"(v) : "l"(p) : "memory");
        if ((int)(v - target) >= 0) break;
        if (n > (1 << 22)) __trap();
    }
}
__device__ __forceinline__ void ld_chunk(uint32_t* r, const void* p) {
    asm volatile("ld.relaxed.gpu.global.v4.u32 {%0, %1, %2, %3}, [%4];"
                 : "=r"(r[0]), "=r"(r[1]), "=r"(r[2]), "=r"(r[3]) : "l"(p) : "memory");
}
__device__ __forceinline__ void st_chunk(void* p, uint32_t a, uint32_t b, uint32_t c, uint32_t d) {
    asm volatile("st.relaxed.gpu.global.v4.u32 [%0], {%1, %2, %3, %4};" ::"l"(p), "r"(a), "r"(b), "r"(c), "r"(d) : "memory");
}
__device__ __forceinline__ uint32_t movm_t(uint32_t a) {
    uint32_t d;
    asm volatile("movmatrix.sync.aligned.m8n8.trans.b16 %0, %1;" : "=r"(d) : "r"(a));
    return d;
}
__device__ __forceinline__ void ld_chunk_if(uint32_t* r, const void* p, int pred) {
    asm volatile("{\n.reg .pred p;\nsetp.ne.s32 p, %5, 0;\n@p ld.relaxed.gpu.global.v4.u32 {%0, %1, %2, %3}, [%4];\n}"
                 : "+r"(r[0]), "+r"(r[1]), "+r"(r[2]), "+r"(r[3]) : "l"(p), "r"(pred) : "memory");
}
__device__ __forceinline__ void wait_landed(const unsigned char* p, int nk, uint32_t tag) {
#pragma unroll 1
    for (int n = 0;; n++) {
        uint32_t bad = 0;
#pragma unroll 1
        for (int i = 0; i < nk; i++) {
            uint32_t w;
            asm volatile("ld.relaxed.gpu.global.u32 %0, [%1];" : "=r"(w) : "l"(p + i * 2048) : "memory");
            bad |= w ^ tag;
        }
        if (!__any_sync(0xffffffffu, bad & 1u)) break;
        if (n > (1 << 18)) __trap();
    }
}
__device__ __forceinline__ void named_sync(int id, int n) { asm volatile("bar.sync %0, %1;" ::"r"(id), "r"(n) : "memory"); }
__device__ __forceinline__ void named_arrive(int id, int n) { asm volatile("bar.arrive %0, %1;" ::"r"(id), "r"(n) : "memory"); }
__device__ __forceinline__ void named_sync_if(int id, int n, int pred) {
    asm volatile("{\n.reg .pred p;\nsetp.ne.s32 p, %2, 0;\n@p bar.sync %0, %1;\n}" ::"r"(id), "r"(n), "r"(pred) : "memory");
}
__device__ __forceinline__ void named_arrive_if(int id, int n, int pred) {
    asm volatile("{\n.reg .pred p;\nsetp.ne.s32 p, %2, 0;\n@p bar.arrive %0, %1;\n}" ::"r"(id), "r"(n), "r"(pred) : "memory");
}
__device__ __forceinline__ int wg_any(int id, int pred) {
    int r;
    asm volatile("{\n.reg .pred p, q;\nsetp.ne.s32 p, %1, 0;\nbarrier.cta.red.or.aligned.pred q, %2, 128, p;\nselp.s32 %0, 1, 0, q;\n}"
                 : "=r"(r) : "r"(pred), "r"(id) : "memory");
    return r;
}
__device__ __forceinline__ void wg_fence() { asm volatile("wgmma.fence.sync.aligned;" ::: "memory"); }
__device__ __forceinline__ void wg_commit() { asm volatile("wgmma.commit_group.sync.aligned;" ::: "memory"); }
template <int N> __device__ __forceinline__ void wg_wait() { asm volatile("wgmma.wait_group.sync.aligned %0;" ::"n"(N) : "memory"); }
template <int N> __device__ __forceinline__ void pin(float (&d)[N]) {
#pragma unroll
    for (int i = 0; i < N; i++) asm volatile("" : "+f"(d[i])::"memory");
}
template <int N> __device__ __forceinline__ void pin(uint32_t (&d)[N]) {
#pragma unroll
    for (int i = 0; i < N; i++) asm volatile("" : "+r"(d[i])::"memory");
}
__device__ __forceinline__ float ex2(float x) { float y; asm("ex2.approx.ftz.f32 %0, %1;" : "=f"(y) : "f"(x)); return y; }
__device__ __forceinline__ uint32_t pack_bf16(float lo, float hi) {
    uint32_t r; asm("cvt.rn.bf16x2.f32 %0, %1, %2;" : "=r"(r) : "f"(hi), "f"(lo)); return r;
}
__device__ __forceinline__ void stsm4(uint32_t a, uint32_t r0, uint32_t r1, uint32_t r2, uint32_t r3) {
    asm volatile("stmatrix.sync.aligned.m8n8.x4.shared.b16 [%0], {%1, %2, %3, %4};"
                 ::"r"(a), "r"(r0), "r"(r1), "r"(r2), "r"(r3) : "memory");
}
__device__ __forceinline__ uint32_t make_desc(uint32_t addr, uint32_t lbo_bytes) {
    return ((addr & 0x3FFFF) >> 4) | ((lbo_bytes >> 4) << 16);
}
template <int TA, int TB>
__device__ __forceinline__ void wgmma_ss_n128_first(float (&d)[64], uint32_t da, uint32_t db) {
    asm volatile(
        "{\n.reg .b64 da, db;\n.reg .b32 hi;\nmov.b32 hi, 0x40000040;\nmov.b64 da, {%64, hi};\nmov.b64 db, {%65, hi};\n"
        "wgmma.mma_async.sync.aligned.m64n128k16.f32.bf16.bf16 "
        "{%0, %1, %2, %3, %4, %5, %6, %7, %8, %9, %10, %11, %12, %13, %14, %15, "
        "%16, %17, %18, %19, %20, %21, %22, %23, %24, %25, %26, %27, %28, %29, %30, %31, "
        "%32, %33, %34, %35, %36, %37, %38, %39, %40, %41, %42, %43, %44, %45, %46, %47, "
        "%48, %49, %50, %51, %52, %53, %54, %55, %56, %57, %58, %59, %60, %61, %62, %63}, "
        "da, db, 0, 1, 1, %66, %67;\n}\n"
        : "=f"(d[0]), "=f"(d[1]), "=f"(d[2]), "=f"(d[3]), "=f"(d[4]), "=f"(d[5]), "=f"(d[6]), "=f"(d[7]),
          "=f"(d[8]), "=f"(d[9]), "=f"(d[10]), "=f"(d[11]), "=f"(d[12]), "=f"(d[13]), "=f"(d[14]), "=f"(d[15]),
          "=f"(d[16]), "=f"(d[17]), "=f"(d[18]), "=f"(d[19]), "=f"(d[20]), "=f"(d[21]), "=f"(d[22]), "=f"(d[23]),
          "=f"(d[24]), "=f"(d[25]), "=f"(d[26]), "=f"(d[27]), "=f"(d[28]), "=f"(d[29]), "=f"(d[30]), "=f"(d[31]),
          "=f"(d[32]), "=f"(d[33]), "=f"(d[34]), "=f"(d[35]), "=f"(d[36]), "=f"(d[37]), "=f"(d[38]), "=f"(d[39]),
          "=f"(d[40]), "=f"(d[41]), "=f"(d[42]), "=f"(d[43]), "=f"(d[44]), "=f"(d[45]), "=f"(d[46]), "=f"(d[47]),
          "=f"(d[48]), "=f"(d[49]), "=f"(d[50]), "=f"(d[51]), "=f"(d[52]), "=f"(d[53]), "=f"(d[54]), "=f"(d[55]),
          "=f"(d[56]), "=f"(d[57]), "=f"(d[58]), "=f"(d[59]), "=f"(d[60]), "=f"(d[61]), "=f"(d[62]), "=f"(d[63])
        : "r"(da), "r"(db), "n"(TA), "n"(TB));
}

template <int TA, int TB>
__device__ __forceinline__ void wgmma_ss_n128(float (&d)[64], uint32_t da, uint32_t db) {
    asm volatile(
        "{\n.reg .b64 da, db;\n.reg .b32 hi;\nmov.b32 hi, 0x40000040;\nmov.b64 da, {%64, hi};\nmov.b64 db, {%65, hi};\n"
        "wgmma.mma_async.sync.aligned.m64n128k16.f32.bf16.bf16 "
        "{%0, %1, %2, %3, %4, %5, %6, %7, %8, %9, %10, %11, %12, %13, %14, %15, "
        "%16, %17, %18, %19, %20, %21, %22, %23, %24, %25, %26, %27, %28, %29, %30, %31, "
        "%32, %33, %34, %35, %36, %37, %38, %39, %40, %41, %42, %43, %44, %45, %46, %47, "
        "%48, %49, %50, %51, %52, %53, %54, %55, %56, %57, %58, %59, %60, %61, %62, %63}, "
        "da, db, 1, 1, 1, %66, %67;\n}\n"
        : "+f"(d[0]), "+f"(d[1]), "+f"(d[2]), "+f"(d[3]), "+f"(d[4]), "+f"(d[5]), "+f"(d[6]), "+f"(d[7]),
          "+f"(d[8]), "+f"(d[9]), "+f"(d[10]), "+f"(d[11]), "+f"(d[12]), "+f"(d[13]), "+f"(d[14]), "+f"(d[15]),
          "+f"(d[16]), "+f"(d[17]), "+f"(d[18]), "+f"(d[19]), "+f"(d[20]), "+f"(d[21]), "+f"(d[22]), "+f"(d[23]),
          "+f"(d[24]), "+f"(d[25]), "+f"(d[26]), "+f"(d[27]), "+f"(d[28]), "+f"(d[29]), "+f"(d[30]), "+f"(d[31]),
          "+f"(d[32]), "+f"(d[33]), "+f"(d[34]), "+f"(d[35]), "+f"(d[36]), "+f"(d[37]), "+f"(d[38]), "+f"(d[39]),
          "+f"(d[40]), "+f"(d[41]), "+f"(d[42]), "+f"(d[43]), "+f"(d[44]), "+f"(d[45]), "+f"(d[46]), "+f"(d[47]),
          "+f"(d[48]), "+f"(d[49]), "+f"(d[50]), "+f"(d[51]), "+f"(d[52]), "+f"(d[53]), "+f"(d[54]), "+f"(d[55]),
          "+f"(d[56]), "+f"(d[57]), "+f"(d[58]), "+f"(d[59]), "+f"(d[60]), "+f"(d[61]), "+f"(d[62]), "+f"(d[63])
        : "r"(da), "r"(db), "n"(TA), "n"(TB));
}

template <int TA, int TB>
__device__ __forceinline__ void wgmma_ss_n192_first(float (&d)[96], uint32_t da, uint32_t db) {
    asm volatile(
        "{\n.reg .b64 da, db;\n.reg .b32 hi;\nmov.b32 hi, 0x40000040;\nmov.b64 da, {%96, hi};\nmov.b64 db, {%97, hi};\n"
        "wgmma.mma_async.sync.aligned.m64n192k16.f32.bf16.bf16 "
        "{%0, %1, %2, %3, %4, %5, %6, %7, %8, %9, %10, %11, %12, %13, %14, %15, "
        "%16, %17, %18, %19, %20, %21, %22, %23, %24, %25, %26, %27, %28, %29, %30, %31, "
        "%32, %33, %34, %35, %36, %37, %38, %39, %40, %41, %42, %43, %44, %45, %46, %47, "
        "%48, %49, %50, %51, %52, %53, %54, %55, %56, %57, %58, %59, %60, %61, %62, %63, "
        "%64, %65, %66, %67, %68, %69, %70, %71, %72, %73, %74, %75, %76, %77, %78, %79, "
        "%80, %81, %82, %83, %84, %85, %86, %87, %88, %89, %90, %91, %92, %93, %94, %95}, "
        "da, db, 0, 1, 1, %98, %99;\n}\n"
        : "=f"(d[0]), "=f"(d[1]), "=f"(d[2]), "=f"(d[3]), "=f"(d[4]), "=f"(d[5]), "=f"(d[6]), "=f"(d[7]),
          "=f"(d[8]), "=f"(d[9]), "=f"(d[10]), "=f"(d[11]), "=f"(d[12]), "=f"(d[13]), "=f"(d[14]), "=f"(d[15]),
          "=f"(d[16]), "=f"(d[17]), "=f"(d[18]), "=f"(d[19]), "=f"(d[20]), "=f"(d[21]), "=f"(d[22]), "=f"(d[23]),
          "=f"(d[24]), "=f"(d[25]), "=f"(d[26]), "=f"(d[27]), "=f"(d[28]), "=f"(d[29]), "=f"(d[30]), "=f"(d[31]),
          "=f"(d[32]), "=f"(d[33]), "=f"(d[34]), "=f"(d[35]), "=f"(d[36]), "=f"(d[37]), "=f"(d[38]), "=f"(d[39]),
          "=f"(d[40]), "=f"(d[41]), "=f"(d[42]), "=f"(d[43]), "=f"(d[44]), "=f"(d[45]), "=f"(d[46]), "=f"(d[47]),
          "=f"(d[48]), "=f"(d[49]), "=f"(d[50]), "=f"(d[51]), "=f"(d[52]), "=f"(d[53]), "=f"(d[54]), "=f"(d[55]),
          "=f"(d[56]), "=f"(d[57]), "=f"(d[58]), "=f"(d[59]), "=f"(d[60]), "=f"(d[61]), "=f"(d[62]), "=f"(d[63]),
          "=f"(d[64]), "=f"(d[65]), "=f"(d[66]), "=f"(d[67]), "=f"(d[68]), "=f"(d[69]), "=f"(d[70]), "=f"(d[71]),
          "=f"(d[72]), "=f"(d[73]), "=f"(d[74]), "=f"(d[75]), "=f"(d[76]), "=f"(d[77]), "=f"(d[78]), "=f"(d[79]),
          "=f"(d[80]), "=f"(d[81]), "=f"(d[82]), "=f"(d[83]), "=f"(d[84]), "=f"(d[85]), "=f"(d[86]), "=f"(d[87]),
          "=f"(d[88]), "=f"(d[89]), "=f"(d[90]), "=f"(d[91]), "=f"(d[92]), "=f"(d[93]), "=f"(d[94]), "=f"(d[95])
        : "r"(da), "r"(db), "n"(TA), "n"(TB));
}

template <int TA, int TB>
__device__ __forceinline__ void wgmma_ss_n192(float (&d)[96], uint32_t da, uint32_t db) {
    asm volatile(
        "{\n.reg .b64 da, db;\n.reg .b32 hi;\nmov.b32 hi, 0x40000040;\nmov.b64 da, {%96, hi};\nmov.b64 db, {%97, hi};\n"
        "wgmma.mma_async.sync.aligned.m64n192k16.f32.bf16.bf16 "
        "{%0, %1, %2, %3, %4, %5, %6, %7, %8, %9, %10, %11, %12, %13, %14, %15, "
        "%16, %17, %18, %19, %20, %21, %22, %23, %24, %25, %26, %27, %28, %29, %30, %31, "
        "%32, %33, %34, %35, %36, %37, %38, %39, %40, %41, %42, %43, %44, %45, %46, %47, "
        "%48, %49, %50, %51, %52, %53, %54, %55, %56, %57, %58, %59, %60, %61, %62, %63, "
        "%64, %65, %66, %67, %68, %69, %70, %71, %72, %73, %74, %75, %76, %77, %78, %79, "
        "%80, %81, %82, %83, %84, %85, %86, %87, %88, %89, %90, %91, %92, %93, %94, %95}, "
        "da, db, 1, 1, 1, %98, %99;\n}\n"
        : "+f"(d[0]), "+f"(d[1]), "+f"(d[2]), "+f"(d[3]), "+f"(d[4]), "+f"(d[5]), "+f"(d[6]), "+f"(d[7]),
          "+f"(d[8]), "+f"(d[9]), "+f"(d[10]), "+f"(d[11]), "+f"(d[12]), "+f"(d[13]), "+f"(d[14]), "+f"(d[15]),
          "+f"(d[16]), "+f"(d[17]), "+f"(d[18]), "+f"(d[19]), "+f"(d[20]), "+f"(d[21]), "+f"(d[22]), "+f"(d[23]),
          "+f"(d[24]), "+f"(d[25]), "+f"(d[26]), "+f"(d[27]), "+f"(d[28]), "+f"(d[29]), "+f"(d[30]), "+f"(d[31]),
          "+f"(d[32]), "+f"(d[33]), "+f"(d[34]), "+f"(d[35]), "+f"(d[36]), "+f"(d[37]), "+f"(d[38]), "+f"(d[39]),
          "+f"(d[40]), "+f"(d[41]), "+f"(d[42]), "+f"(d[43]), "+f"(d[44]), "+f"(d[45]), "+f"(d[46]), "+f"(d[47]),
          "+f"(d[48]), "+f"(d[49]), "+f"(d[50]), "+f"(d[51]), "+f"(d[52]), "+f"(d[53]), "+f"(d[54]), "+f"(d[55]),
          "+f"(d[56]), "+f"(d[57]), "+f"(d[58]), "+f"(d[59]), "+f"(d[60]), "+f"(d[61]), "+f"(d[62]), "+f"(d[63]),
          "+f"(d[64]), "+f"(d[65]), "+f"(d[66]), "+f"(d[67]), "+f"(d[68]), "+f"(d[69]), "+f"(d[70]), "+f"(d[71]),
          "+f"(d[72]), "+f"(d[73]), "+f"(d[74]), "+f"(d[75]), "+f"(d[76]), "+f"(d[77]), "+f"(d[78]), "+f"(d[79]),
          "+f"(d[80]), "+f"(d[81]), "+f"(d[82]), "+f"(d[83]), "+f"(d[84]), "+f"(d[85]), "+f"(d[86]), "+f"(d[87]),
          "+f"(d[88]), "+f"(d[89]), "+f"(d[90]), "+f"(d[91]), "+f"(d[92]), "+f"(d[93]), "+f"(d[94]), "+f"(d[95])
        : "r"(da), "r"(db), "n"(TA), "n"(TB));
}

template <int TB>
__device__ __forceinline__ void wgmma_rs_n128(float (&d)[64], uint32_t a0, uint32_t a1, uint32_t a2, uint32_t a3, uint32_t db) {
    asm volatile(
        "{\n.reg .b64 db;\n.reg .b32 hi;\nmov.b32 hi, 0x40000040;\nmov.b64 db, {%68, hi};\n"
        "wgmma.mma_async.sync.aligned.m64n128k16.f32.bf16.bf16 "
        "{%0, %1, %2, %3, %4, %5, %6, %7, %8, %9, %10, %11, %12, %13, %14, %15, "
        "%16, %17, %18, %19, %20, %21, %22, %23, %24, %25, %26, %27, %28, %29, %30, %31, "
        "%32, %33, %34, %35, %36, %37, %38, %39, %40, %41, %42, %43, %44, %45, %46, %47, "
        "%48, %49, %50, %51, %52, %53, %54, %55, %56, %57, %58, %59, %60, %61, %62, %63}, "
        "{%64, %65, %66, %67}, db, 1, 1, 1, %69;\n}\n"
        : "+f"(d[0]), "+f"(d[1]), "+f"(d[2]), "+f"(d[3]), "+f"(d[4]), "+f"(d[5]), "+f"(d[6]), "+f"(d[7]),
          "+f"(d[8]), "+f"(d[9]), "+f"(d[10]), "+f"(d[11]), "+f"(d[12]), "+f"(d[13]), "+f"(d[14]), "+f"(d[15]),
          "+f"(d[16]), "+f"(d[17]), "+f"(d[18]), "+f"(d[19]), "+f"(d[20]), "+f"(d[21]), "+f"(d[22]), "+f"(d[23]),
          "+f"(d[24]), "+f"(d[25]), "+f"(d[26]), "+f"(d[27]), "+f"(d[28]), "+f"(d[29]), "+f"(d[30]), "+f"(d[31]),
          "+f"(d[32]), "+f"(d[33]), "+f"(d[34]), "+f"(d[35]), "+f"(d[36]), "+f"(d[37]), "+f"(d[38]), "+f"(d[39]),
          "+f"(d[40]), "+f"(d[41]), "+f"(d[42]), "+f"(d[43]), "+f"(d[44]), "+f"(d[45]), "+f"(d[46]), "+f"(d[47]),
          "+f"(d[48]), "+f"(d[49]), "+f"(d[50]), "+f"(d[51]), "+f"(d[52]), "+f"(d[53]), "+f"(d[54]), "+f"(d[55]),
          "+f"(d[56]), "+f"(d[57]), "+f"(d[58]), "+f"(d[59]), "+f"(d[60]), "+f"(d[61]), "+f"(d[62]), "+f"(d[63])
        : "r"(a0), "r"(a1), "r"(a2), "r"(a3), "r"(db), "n"(TB));
}

template <int TB>
__device__ __forceinline__ void wgmma_rs_n128_p(float (&d)[64], uint32_t a0, uint32_t a1, uint32_t a2, uint32_t a3, uint32_t db, int acc) {
    asm volatile(
        "{\n.reg .b64 db;\n.reg .b32 hi;\n.reg .pred p;\nsetp.ne.s32 p, %70, 0;\nmov.b32 hi, 0x40000040;\nmov.b64 db, {%68, hi};\n"
        "wgmma.mma_async.sync.aligned.m64n128k16.f32.bf16.bf16 "
        "{%0, %1, %2, %3, %4, %5, %6, %7, %8, %9, %10, %11, %12, %13, %14, %15, "
        "%16, %17, %18, %19, %20, %21, %22, %23, %24, %25, %26, %27, %28, %29, %30, %31, "
        "%32, %33, %34, %35, %36, %37, %38, %39, %40, %41, %42, %43, %44, %45, %46, %47, "
        "%48, %49, %50, %51, %52, %53, %54, %55, %56, %57, %58, %59, %60, %61, %62, %63}, "
        "{%64, %65, %66, %67}, db, p, 1, 1, %69;\n}\n"
        : "+f"(d[0]), "+f"(d[1]), "+f"(d[2]), "+f"(d[3]), "+f"(d[4]), "+f"(d[5]), "+f"(d[6]), "+f"(d[7]),
          "+f"(d[8]), "+f"(d[9]), "+f"(d[10]), "+f"(d[11]), "+f"(d[12]), "+f"(d[13]), "+f"(d[14]), "+f"(d[15]),
          "+f"(d[16]), "+f"(d[17]), "+f"(d[18]), "+f"(d[19]), "+f"(d[20]), "+f"(d[21]), "+f"(d[22]), "+f"(d[23]),
          "+f"(d[24]), "+f"(d[25]), "+f"(d[26]), "+f"(d[27]), "+f"(d[28]), "+f"(d[29]), "+f"(d[30]), "+f"(d[31]),
          "+f"(d[32]), "+f"(d[33]), "+f"(d[34]), "+f"(d[35]), "+f"(d[36]), "+f"(d[37]), "+f"(d[38]), "+f"(d[39]),
          "+f"(d[40]), "+f"(d[41]), "+f"(d[42]), "+f"(d[43]), "+f"(d[44]), "+f"(d[45]), "+f"(d[46]), "+f"(d[47]),
          "+f"(d[48]), "+f"(d[49]), "+f"(d[50]), "+f"(d[51]), "+f"(d[52]), "+f"(d[53]), "+f"(d[54]), "+f"(d[55]),
          "+f"(d[56]), "+f"(d[57]), "+f"(d[58]), "+f"(d[59]), "+f"(d[60]), "+f"(d[61]), "+f"(d[62]), "+f"(d[63])
        : "r"(a0), "r"(a1), "r"(a2), "r"(a3), "r"(db), "n"(TB), "r"(acc));
}

template <int TB>
__device__ __forceinline__ void wgmma_rs_n128_first(float (&d)[64], uint32_t a0, uint32_t a1, uint32_t a2, uint32_t a3, uint32_t db) {
    asm volatile(
        "{\n.reg .b64 db;\n.reg .b32 hi;\nmov.b32 hi, 0x40000040;\nmov.b64 db, {%68, hi};\n"
        "wgmma.mma_async.sync.aligned.m64n128k16.f32.bf16.bf16 "
        "{%0, %1, %2, %3, %4, %5, %6, %7, %8, %9, %10, %11, %12, %13, %14, %15, "
        "%16, %17, %18, %19, %20, %21, %22, %23, %24, %25, %26, %27, %28, %29, %30, %31, "
        "%32, %33, %34, %35, %36, %37, %38, %39, %40, %41, %42, %43, %44, %45, %46, %47, "
        "%48, %49, %50, %51, %52, %53, %54, %55, %56, %57, %58, %59, %60, %61, %62, %63}, "
        "{%64, %65, %66, %67}, db, 0, 1, 1, %69;\n}\n"
        : "=f"(d[0]), "=f"(d[1]), "=f"(d[2]), "=f"(d[3]), "=f"(d[4]), "=f"(d[5]), "=f"(d[6]), "=f"(d[7]),
          "=f"(d[8]), "=f"(d[9]), "=f"(d[10]), "=f"(d[11]), "=f"(d[12]), "=f"(d[13]), "=f"(d[14]), "=f"(d[15]),
          "=f"(d[16]), "=f"(d[17]), "=f"(d[18]), "=f"(d[19]), "=f"(d[20]), "=f"(d[21]), "=f"(d[22]), "=f"(d[23]),
          "=f"(d[24]), "=f"(d[25]), "=f"(d[26]), "=f"(d[27]), "=f"(d[28]), "=f"(d[29]), "=f"(d[30]), "=f"(d[31]),
          "=f"(d[32]), "=f"(d[33]), "=f"(d[34]), "=f"(d[35]), "=f"(d[36]), "=f"(d[37]), "=f"(d[38]), "=f"(d[39]),
          "=f"(d[40]), "=f"(d[41]), "=f"(d[42]), "=f"(d[43]), "=f"(d[44]), "=f"(d[45]), "=f"(d[46]), "=f"(d[47]),
          "=f"(d[48]), "=f"(d[49]), "=f"(d[50]), "=f"(d[51]), "=f"(d[52]), "=f"(d[53]), "=f"(d[54]), "=f"(d[55]),
          "=f"(d[56]), "=f"(d[57]), "=f"(d[58]), "=f"(d[59]), "=f"(d[60]), "=f"(d[61]), "=f"(d[62]), "=f"(d[63])
        : "r"(a0), "r"(a1), "r"(a2), "r"(a3), "r"(db), "n"(TB));
}

template <bool B> struct BoolC { static constexpr bool value = B; };

struct Params {
    CUtensorMap x, wq, k, v, wo, out;
    const unsigned char *xp, *wqp;
};

__global__ void __cluster_dims__(2, 1, 1) __launch_bounds__(NTHREADS, 1)
gqa_fused_kernel(const __grid_constant__ Params p, __nv_bfloat16* __restrict__ out) {
    extern __shared__ __align__(1024) unsigned char smem_raw[];
    const uint32_t sb = smem_u32(smem_raw);
    const uint32_t bars = sb + SM_BAR;
    const int tid = threadIdx.x;
    const int cta = blockIdx.x;
    const int cl = cta >> 1, rank = cta & 1;
    uint64_t pol_stream;
    asm volatile("createpolicy.fractional.L2::evict_first.b64 %0, 1.0;" : "=l"(pol_stream));
    const int p1_n = cl, p1_mh = rank;
    const uint32_t t_start = clock32();
    auto first_chunk = [&](int c) {
        const uint32_t fb = bars + 8 * (B_FULL + c), dst = sb + SM_RING + c * 32768;
        mbar_expect_tx(fb, 32768);
        while (clock32() - t_start < c * WD) {}
        tma2d(dst + 24576, &p.wq, fb, p1_n * 64, c * 64, pol_stream);
        while (clock32() - t_start < c * XD) {}
        tma2d(dst, &p.x, fb, c * 64, p1_mh * 192, pol_stream);
    };
    if ((tid & 0x19f) == 0x180) {
        const int c = (tid >> 5) - 12;
        mbar_init(bars + 8 * (B_FULL + c), 1);
        fence_async_smem();
        if (c < 2) first_chunk(c);
        else mbar_init(bars + 8 * (B_FULL + c + 2), 1);
    }
    else if (tid < 384) {
        if (tid == 352) asm volatile("prefetch.tensormap [%0];" ::"l"(&p.wq) : "memory");
        if (tid == 320) asm volatile("prefetch.tensormap [%0];" ::"l"(&p.x) : "memory");
        if (tid < 64)
            asm volatile("prefetch.global.L2 [%0];" ::"l"(p.wqp + (size_t)(tid * 2 + rank) * 8192 + cl * 128) : "memory");
        else if (tid >= 256 && tid < 256 + 6)
            asm volatile("prefetch.global.L2 [%0];" ::"l"(p.xp + (size_t)(cta * 3 + (tid - 256) % 3) * 2048 + ((tid - 256) / 3) * 128) : "memory");
    }
    const int warp = __shfl_sync(0xffffffffu, tid >> 5, 0), lane = tid & 31;
    const int row = (cl < 4) ? cl : (cl < 36 ? (cl - 4) >> 3 : (cl - 36) / 7);
    const int col = (cl < 4) ? 15 : (cl < 36 ? (cl - 4) & 7 : 8 + (cl - 36) % 7);
    const int a_u = col * 2 + (row >> 1);
    const int a_b = a_u >> 2, a_hq = (a_u & 3) * 2 + (row & 1);
    const int p3_mh = col >> 3, p3_hq = col & 7, p3_n = row * 2 + rank;
    if (lane == 0 && warp < 12) {
        if (warp < 9) mbar_init(bars + 8 * (B_EMPTY + warp), warp < 6 ? 12 : 1);
        else {
            if (warp < 11) {
                asm volatile("prefetch.tensormap [%0];" ::"l"(&p.k + 2 * (warp - 9)) : "memory");
                asm volatile("prefetch.tensormap [%0];" ::"l"(&p.v + 2 * (warp - 9)) : "memory");
            }
            if (warp == 11) mbar_init(bars + 8 * B_P3GO, 1);
            if (sb & 1023) __trap();
        }
    }
    __syncthreads();

    if (warp < 12) {
        asm volatile("setmaxnreg.inc.sync.aligned.u32 160;");
        const int wg = warp >> 2, wi = warp & 3;
        const int g = lane >> 2;
        unsigned epoch = 0;
        if (wg == 0) {
            asm volatile("barrier.cluster.arrive.relaxed.aligned;" ::: "memory");
            float d[96];
            {
                const uint32_t st = sb + SM_RING;
                mbar_wait(bars + 8 * B_FULL, 0);
                const uint32_t da = make_desc(st + 24576, 16);
                const uint32_t db = make_desc(st, 16);
                wg_fence();
                wgmma_ss_n192_first<1, 0>(d, da, db);
#pragma unroll
                for (int kk = 1; kk < 4; kk++) wgmma_ss_n192<1, 0>(d, da + kk * 128, db + kk * 2);
                wg_commit();
            }
            int slot = 1, pslot = 0; uint32_t ph = 0;
#pragma unroll 1
            for (int c = 1; c < 16; c++) {
                if (c == 12) {
                    asm volatile("barrier.cluster.wait.aligned;" ::: "memory");
                    mbar_wait(bars + 8 * B_EPOCH, 0);
                    asm volatile("ld.shared.u32 %0, [%1];" : "=r"(epoch) : "r"(sb + SM_EPOCHV) : "memory");
                }
                const uint32_t st = sb + SM_RING + slot * 32768;
                mbar_wait(bars + 8 * (B_FULL + slot), ph);
                const uint32_t da = make_desc(st + 24576, 16);
                const uint32_t db = make_desc(st, 16);
                wg_fence();
#pragma unroll
                for (int kk = 0; kk < 4; kk++) wgmma_ss_n192<1, 0>(d, da + kk * 128, db + kk * 2);
                wg_commit();
                wg_wait<1>();
                mbar_arrive_if(bars + 8 * (B_EMPTY + pslot), 3, lane == 0);
                pslot = slot;
                if (++slot == 6) { slot = 0; ph ^= 1; }
            }
            wg_wait<0>();
            pin(d);
            named_arrive(4, 384);
            mbar_arrive_if(bars + 8 * (B_EMPTY + 3), 3, lane == 0);
            {
                const uint32_t tg = ~epoch & 1u;
                unsigned char* dst = g_qs + (size_t)(p1_mh * 32 + (p1_n >> 3)) * 49152 + ((p1_n >> 1) & 3) * 4096 +
                                     ((p1_n & 1) * 4 + wi) * 512 + lane * 16;
#pragma unroll
                for (int w = 2; w >= 0; w--) {
#pragma unroll
                    for (int bl = 0; bl < 4; bl++) {
                        const int j = (bl * 3 + w) * 2;
                        const uint32_t a0 = movm_t(pack_bf16(d[4 * j] * QSCALE, d[4 * j + 1] * QSCALE));
                        const uint32_t a1 = movm_t(pack_bf16(d[4 * j + 4] * QSCALE, d[4 * j + 5] * QSCALE));
                        const uint32_t a2 = movm_t(pack_bf16(d[4 * j + 2] * QSCALE, d[4 * j + 3] * QSCALE));
                        const uint32_t a3 = movm_t(pack_bf16(d[4 * j + 6] * QSCALE, d[4 * j + 7] * QSCALE));
                        st_chunk(dst + (size_t)bl * 393216 + w * 16384, (a0 & ~1u) | tg, a1, a2, a3);
                    }
                    named_sync(3, 128);
                    if (tid == 0) red_relaxed(&g_cnt[CNT_Q(p1_mh, p1_n >> 3, w)]);
                }
            }
        } else {
            if (lane == 0) {
#pragma unroll 1
                for (int i = B_ML + warp - 4; i < B_P3GO; i += 8) {
                    mbar_init(bars + 8 * i, 1);
                    mbar_expect_tx(bars + 8 * i, i < B_XB ? 128 : 4096);
                }
                asm volatile("fence.mbarrier_init.release.cluster;" ::: "memory");
            }
            __syncwarp();
            asm volatile("barrier.cluster.arrive.relaxed.aligned;" ::: "memory");
            asm volatile("barrier.cluster.wait.aligned;" ::: "memory");
            mbar_wait(bars + 8 * B_EPOCH, 0);
            asm volatile("ld.shared.u32 %0, [%1];" : "=r"(epoch) : "r"(sb + SM_EPOCHV) : "memory");
            named_sync(4, 384);
        }

        const uint32_t qbase = sb + SM_Q + wg * 16384;
        const uint32_t tag = ~epoch & 1u;
        {
            const unsigned char* src = g_qs + (size_t)(a_b * 8 + a_hq) * 49152 + wg * 16384 + wi * 4096 + lane * 16;
            if ((tid & 127) == 0) {
                const uint32_t t0 = clock32();
                if (wg) while (clock32() - t0 < 1100 - 250 * wg) {}
                poll_ge(&g_cnt[CNT_Q(a_b >> 2, a_hq, wg)], (epoch + 1) * 8);
            }
            __syncwarp();
            named_sync(5 + wg, 128);
            uint32_t qv[32];
#pragma unroll 1
            for (int n = 0;; n++) {
#pragma unroll
                for (int i = 0; i < 8; i++) ld_chunk(qv + 4 * i, src + i * 512);
                uint32_t bad = 0;
#pragma unroll
                for (int i = 0; i < 8; i++) bad |= qv[4 * i] ^ tag;
                if (!__any_sync(0xffffffffu, bad & 1u)) break;
                if (n > (1 << 18)) __trap();
            }
            const int q = lane >> 3, r = lane & 7;
            const uint32_t rowa = qbase + (wi * 16 + (q & 1) * 8 + r) * 128;
#pragma unroll
            for (int i = 0; i < 8; i++)
                stsm4(rowa + (i >> 2) * 8192 + ((((2 * i + (q >> 1)) & 7) ^ r) << 4), qv[4 * i], qv[4 * i + 1], qv[4 * i + 2],
                      qv[4 * i + 3]);
            fence_async_smem();
            named_sync(5 + wg, 128);
            mbar_arrive_if(bars + 8 * B_QGO, 1, tid == 256);
        }

        float o[64];
#pragma unroll
        for (int i = 0; i < 64; i++) asm volatile("" : "=f"(o[i]));
        float m0 = 0.f, m1 = 0.f, l0 = 0.f, l1 = 0.f, lo = 5.9604645e-8f;
        const uint32_t dq = make_desc(qbase, 16);
        int slot = 4; uint32_t qp = 0;
        const int lane0 = (lane == 0);
        mbar_wait(bars + 8 * (B_FULL + 4), 0);
        named_sync_if(8 + wg, 256, wg < 2);
        int j = 0;
        auto tile = [&](auto safe_tag) -> bool {
            constexpr bool SAFE = decltype(safe_tag)::value;
            const int vslot = (slot == 4) ? 0 : slot + 1;
            const uint32_t vph = qp ^ (slot == 4);
            const uint32_t dk = make_desc(sb + SM_RING + slot * 32768, 16);
            const uint32_t dv = make_desc(sb + SM_RING + vslot * 32768, 16384);
            float s[64];
            wg_fence();
            wgmma_ss_n128_first<0, 0>(s, dq, dk);
#pragma unroll
            for (int kk = 1; kk < 8; kk++)
                wgmma_ss_n128<0, 0>(s, dq + (kk >> 2) * 512 + (kk & 3) * 2, dk + (kk >> 2) * 1024 + (kk & 3) * 2);
            wg_commit();
            if constexpr (!SAFE) named_arrive_if(7 + wg, 256, (j == 0) & (wg > 0));
            const bool vok = mbar_test(bars + 8 * (B_FULL + vslot), vph);
            wg_wait<0>();
            pin(s);
            if constexpr (SAFE) {
                float t0 = s[0], t1 = s[2];
#pragma unroll
                for (int i = 0; i < 16; i++) {
                    t0 = fmaxf(t0, fmaxf(s[4 * i], s[4 * i + 1]));
                    t1 = fmaxf(t1, fmaxf(s[4 * i + 2], s[4 * i + 3]));
                }
                t0 = fmaxf(t0, __shfl_xor_sync(0xffffffffu, t0, 1));
                t1 = fmaxf(t1, __shfl_xor_sync(0xffffffffu, t1, 1));
                t0 = fmaxf(t0, __shfl_xor_sync(0xffffffffu, t0, 2));
                t1 = fmaxf(t1, __shfl_xor_sync(0xffffffffu, t1, 2));
                if (j > 0) { t0 = fmaxf(t0, m0); t1 = fmaxf(t1, m1); }
                const float al0 = ex2(fminf(m0 - t0, 0.f)), al1 = ex2(fminf(m1 - t1, 0.f));
                m0 = t0; m1 = t1;
                l0 *= al0; l1 *= al1;
#pragma unroll
                for (int i = 0; i < 64; i++) { o[i] *= (i & 2) ? al1 : al0; s[i] -= (i & 2) ? t1 : t0; }
            }
            uint32_t pk[32];
            float r0 = 0.f, r1 = 0.f;
#pragma unroll
            for (int k = 0; k < 8; k++) {
                float e[8];
#pragma unroll
                for (int i = 0; i < 8; i++) e[i] = ex2(s[8 * k + i]);
                r0 += (e[0] + e[1]) + (e[4] + e[5]);
                r1 += (e[2] + e[3]) + (e[6] + e[7]);
#pragma unroll
                for (int i = 0; i < 4; i++) pk[4 * k + i] = pack_bf16(e[2 * i], e[2 * i + 1]);
            }
            if constexpr (!SAFE) {
                const int bad = !((r0 <= 16777216.f) & (r1 <= 16777216.f) & (r0 >= lo) & (r1 >= lo));
                if (__builtin_expect(__any_sync(0xffffffffu, wg_any(5 + wg, bad)), 0)) return false;
                lo = -1.f;
            }
            if (__builtin_expect(!vok, 0)) mbar_wait(bars + 8 * (B_FULL + vslot), vph);
            wg_fence();
            wgmma_rs_n128_p<1>(o, pk[0], pk[1], pk[2], pk[3], dv, j);
#pragma unroll
            for (int kk = 1; kk < 8; kk++)
                wgmma_rs_n128<1>(o, pk[4 * kk], pk[4 * kk + 1], pk[4 * kk + 2], pk[4 * kk + 3], dv + kk * 128);
            wg_commit();
            mbar_arrive_if(bars + 8 * (B_EMPTY + slot), 1, lane0);
            l0 += r0; l1 += r1;
            if (__builtin_expect(j == 7, 0)) {
                l0 += __shfl_xor_sync(0xffffffffu, l0, 1); l1 += __shfl_xor_sync(0xffffffffu, l1, 1);
                l0 += __shfl_xor_sync(0xffffffffu, l0, 2); l1 += __shfl_xor_sync(0xffffffffu, l1, 2);
                asm volatile("{\n.reg .pred p;\n.reg .b32 ra, rb;\nsetp.eq.s32 p, %6, 0;\n"
                             "mapa.shared::cluster.u32 ra, %0, %7;\nmapa.shared::cluster.u32 rb, %5, %7;\n"
                             "@p st.async.shared::cluster.mbarrier::complete_tx::bytes.v4.f32 [ra], {%1, %2, %3, %4}, [rb];\n}"
                             ::"r"(sb + SM_ML + warp * 128 + g * 16), "f"(m0), "f"(l0), "f"(m1), "f"(l1),
                               "r"(bars + 8 * (B_ML + warp)), "r"(lane & 3), "r"(rank ^ 1) : "memory");
            }
            slot = (vslot == 4) ? 0 : vslot + 1;
            qp = vph ^ (vslot == 4);
            mbar_wait(bars + 8 * (B_FULL + slot), qp);
            wg_wait<0>();
            pin(o);
            mbar_arrive_if(bars + 8 * (B_EMPTY + vslot), 1, lane0);
            return true;
        };
#pragma unroll 1
        for (; j < 8; j++)
            if (!tile(BoolC<false>{})) break;
#pragma unroll 1
        for (; j < 8; j++) tile(BoolC<true>{});
        {
            mbar_wait(bars + 8 * (B_ML + warp), 0);
            const uint32_t xb = qbase + wi * 2048 + lane * 16;
            if ((wi >> 1) != rank) {
                uint32_t ra, rb;
                asm volatile("mapa.shared::cluster.u32 %0, %1, %2;" : "=r"(ra) : "r"(xb), "r"(rank ^ 1));
                asm volatile("mapa.shared::cluster.u32 %0, %1, %2;" : "=r"(rb) : "r"(bars + 8 * (B_XB + warp)), "r"(rank ^ 1));
#pragma unroll
                for (int i = 0; i < 8; i++)
                    asm volatile("st.async.shared::cluster.mbarrier::complete_tx::bytes.v4.b32 [%0], {%1, %2, %3, %4}, [%5];"
                                 ::"r"(ra + (i >> 2) * 8192 + (i & 3) * 512),
                                   "r"(pack_bf16(o[8 * i], o[8 * i + 1])), "r"(pack_bf16(o[8 * i + 2], o[8 * i + 3])),
                                   "r"(pack_bf16(o[8 * i + 4], o[8 * i + 5])), "r"(pack_bf16(o[8 * i + 6], o[8 * i + 7])),
                                   "r"(rb) : "memory");
            } else {
                float pm0, pl0, pm1, pl1;
                asm volatile("ld.shared.v4.f32 {%0, %1, %2, %3}, [%4];" : "=f"(pm0), "=f"(pl0), "=f"(pm1), "=f"(pl1)
                             : "r"(sb + SM_ML + warp * 128 + g * 16) : "memory");
                const float M0 = fmaxf(m0, pm0), M1 = fmaxf(m1, pm1);
                const float a0 = ex2(m0 - M0), b0 = ex2(pm0 - M0);
                const float a1 = ex2(m1 - M1), b1 = ex2(pm1 - M1);
                const float i0 = __fdividef(1.f, l0 * a0 + pl0 * b0), i1 = __fdividef(1.f, l1 * a1 + pl1 * b1);
                const float w0 = a0 * i0, w1 = a1 * i1;
                const uint32_t v0 = pack_bf16(b0 * i0, b0 * i0), v1 = pack_bf16(b1 * i1, b1 * i1);
                uint32_t y[32];
#pragma unroll
                for (int k = 0; k < 32; k++) y[k] = pack_bf16(o[2 * k] * ((k & 1) ? w1 : w0), o[2 * k + 1] * ((k & 1) ? w1 : w0));
                pin(y);
                mbar_wait(bars + 8 * (B_XB + warp), 0);
                unsigned char* dst = g_os + (size_t)(((a_b >> 2) * 8 + a_hq) * 3 + wg) * 65536 +
                                     wi * 16384 + (a_b & 3) * 512 + lane * 16;
#pragma unroll
                for (int i = 0; i < 8; i++) {
                    uint32_t x[4];
                    asm volatile("ld.shared.v4.u32 {%0, %1, %2, %3}, [%4];" : "=r"(x[0]), "=r"(x[1]), "=r"(x[2]), "=r"(x[3])
                                 : "r"(xb + (i >> 2) * 8192 + (i & 3) * 512) : "memory");
#pragma unroll
                    for (int k = 0; k < 4; k++)
                        asm("fma.rn.bf16x2 %0, %0, %1, %2;" : "+r"(x[k]) : "r"((k & 1) ? v1 : v0), "r"(y[4 * i + k]));
                    st_chunk(dst + i * 2048, (x[0] & ~1u) | tag, x[1], x[2], x[3]);
                }
                __syncwarp();
                if (lane == 0) red_relaxed(&g_cnt[CNT_O(a_b >> 2, a_hq, wg)]);
            }
        }

        {
            const unsigned char* src = g_os + (size_t)((p3_mh * 8 + p3_hq) * 3 + wg) * 65536 + wi * 512 + lane * 16;
            if (lane == 0) {
                mbar_wait(bars + 8 * B_ZOK, 0);
                fence_async_global();
                if (wi == 0) poll_ge(&g_cnt[CNT_O(p3_mh, p3_hq, wg)], (epoch + 1) * 16);
            }
            __syncwarp();
            named_sync(5 + wg, 128);
            float acc[64];
            uint32_t af[NS][4 * KS];
#pragma unroll
            for (int si = 0; si < NS; si++)
#pragma unroll
                for (int i = 0; i < KS; i++) ld_chunk(af[si] + 4 * i, src + (si * KS + i) * 2048);
            mbar_arrive_if(bars + 8 * B_P3GO, 1, tid == 256);
#pragma unroll
            for (int gi = 0; gi * KS < 32; gi++) {
                uint32_t(&a)[4 * KS] = af[gi % NS];
                const int k0 = gi * KS, nk = (32 - k0 < KS) ? 32 - k0 : KS;
                {
                    uint32_t df = 0;
#pragma unroll
                    for (int i = 0; i < nk; i++) df |= a[4 * i] ^ tag;
                    const int bad = __any_sync(0xffffffffu, df & 1u);
                    if (bad) wait_landed(src + k0 * 2048, nk, tag);
#pragma unroll
                    for (int i = 0; i < nk; i++) ld_chunk_if(a + 4 * i, src + (k0 + i) * 2048, bad);
                }
                if (gi == 0 || ((k0 + nk - 1) >> 3) != ((k0 - 1) >> 3)) mbar_wait(bars + 8 * (B_FULL + ((k0 + nk - 1) >> 3)), 0);
                wg_fence();
#pragma unroll
                for (int i = 0; i < nk; i++) {
                    const int ks = k0 + i;
                    const uint32_t db = make_desc(sb + SM_RING + ks * 4096 - (ks & 7) * 2048, 16384);
                    if (ks == 0) wgmma_rs_n128_first<1>(acc, a[0], a[1], a[2], a[3], db);
                    else wgmma_rs_n128<1>(acc, a[4 * i], a[4 * i + 1], a[4 * i + 2], a[4 * i + 3], db);
                }
                wg_commit();
                if (gi >= 1 && (gi - 1 + NS) * KS < 32) {
                    wg_wait<1>();
#pragma unroll
                    for (int i = 0; i < KS; i++)
                        if ((gi - 1 + NS) * KS + i < 32) ld_chunk(af[(gi - 1) % NS] + 4 * i, src + ((gi - 1 + NS) * KS + i) * 2048);
                }
            }
            wg_wait<0>();
            pin(acc);
            const int q = lane >> 3, r = lane & 7;
            const uint32_t rowa = qbase + (wi * 16 + (q & 1) * 8 + r) * 128;
#pragma unroll
            for (int j = 0; j < 16; j += 2) {
                const int cc = j + (q >> 1);
                stsm4(rowa + (j >> 3) * 8192 + (((cc & 7) ^ r) << 4),
                      pack_bf16(acc[4 * j], acc[4 * j + 1]), pack_bf16(acc[4 * j + 2], acc[4 * j + 3]),
                      pack_bf16(acc[4 * j + 4], acc[4 * j + 5]), pack_bf16(acc[4 * j + 6], acc[4 * j + 7]));
            }
            fence_async_smem();
            __syncwarp();
            if (lane == 0) {
                tma3d_red_add(&p.out, qbase + wi * 2048, p3_n * 128, wg * 16, p3_mh * 4 + wi);
                tma3d_red_add(&p.out, qbase + 8192 + wi * 2048, p3_n * 128 + 64, wg * 16, p3_mh * 4 + wi);
                bulk_commit();
                bulk_wait0_read();
            }
            __syncwarp();
        }
    } else {
        asm volatile("setmaxnreg.dec.sync.aligned.u32 32;");
        asm volatile("barrier.cluster.arrive.relaxed.aligned;" ::: "memory");
        if (lane == 0) {
            fence_async_smem();
            first_chunk(warp < 14 ? warp - 8 : warp - 12);
        }
        if (warp == 12) {
            if (lane == 0) {
                const int kv_row0 = (a_b * 4 + (a_hq >> 1)) * 2048 + rank * 1024;
#pragma unroll 1
                for (int c = 6; c < 16; c++) {
                    const int sl = (c < 12) ? c - 6 : c - 12;
                    const uint32_t fb = bars + 8 * (B_FULL + sl), dst = sb + SM_RING + sl * 32768;
                    mbar_wait(bars + 8 * (B_EMPTY + sl), c >= 12);
                    mbar_expect_tx(fb, 32768);
                    tma2d(dst + 24576, &p.wq, fb, p1_n * 64, c * 64, pol_stream);
                    tma2d(dst, &p.x, fb, c * 64, p1_mh * 192, pol_stream);
                }
                uint32_t last = 0;
                int slot = 4; uint32_t qp = 0;
#pragma unroll 1
                for (int t = 0; t < 20; t++) {
                    const uint32_t fb = bars + 8 * (B_FULL + slot), dst = sb + SM_RING + slot * 32768;
                    const CUtensorMap* m = (t >= 16) ? &p.wo : ((t & 1) ? &p.v : &p.k);
                    const int r = (t >= 16) ? p3_hq * 512 + (t - 16) * 128 : kv_row0 + (t >> 1) * 128;
                    const int c0 = (t >= 16) ? p3_n * 128 : 0;
                    mbar_wait(bars + 8 * (B_EMPTY + slot), qp ^ 1);
                    mbar_expect_tx(fb, 32768);
                    if (t >= 2 && t < 8) while (clock32() - last < PACE) {}
                    if (t == 19) {
                        mbar_wait(bars + 8 * B_P3GO, 0);
                        last = clock32();
                        while (clock32() - last < 700) {}
                    }
                    last = clock32();
                    tma2d(dst, m, fb, c0, r, pol_stream);
                    if (t == 19) while (clock32() - last < 700) {}
                    if (t == 0) while (clock32() - last < 400) {}
                    if (t == 1) {
                        mbar_wait(bars + 8 * B_QGO, 0);
                        last = clock32() - PACE;
                    }
                    tma2d(dst + 16384, m, fb, c0 + 64, r, pol_stream);
                    if (++slot == 5) { slot = 0; qp ^= 1; }
                }
            }
        } else {
            if (tid == 480) {
                unsigned ticket;
                asm volatile("atom.add.relaxed.gpu.global.u32 %0, [%1], 1;" : "=r"(ticket) : "l"(&g_cnt[CNT_TICKET]) : "memory");
                asm volatile("st.shared.u32 [%0], %1;" ::"r"(sb + SM_EPOCHV), "r"(ticket / NCTA) : "memory");
                mbar_arrive(bars + 8 * B_EPOCH);
            }
            __syncwarp();
            if (warp == 14) {
                mbar_wait(bars + 8 * B_QGO, 0);
                unsigned epoch;
                asm volatile("ld.shared.u32 %0, [%1];" : "=r"(epoch) : "r"(sb + SM_EPOCHV) : "memory");
                uint4* zz = reinterpret_cast<uint4*>(reinterpret_cast<unsigned char*>(out) + (size_t)cta * 6144);
                __nanosleep(3000);
#pragma unroll 1
                for (int i = 0; i < 12; i++) { zz[lane + i * 32] = make_uint4(0, 0, 0, 0); __nanosleep(50); }
                __syncwarp();
                if (lane == 0) asm volatile("red.release.gpu.global.add.u32 [%0], 1;" ::"l"(&g_cnt[CNT_ZERO]) : "memory");
                __syncwarp();
                if (lane == 0) {
                    int n = 0;
                    while ((int)(ld_acquire(&g_cnt[CNT_ZERO]) - (epoch + 1) * NCTA) < 0) {
                        __nanosleep(500);
                        if (++n > (1 << 20)) __trap();
                    }
                    mbar_arrive(bars + 8 * B_ZOK);
                }
            }
        }
        __syncwarp();
        asm volatile("barrier.cluster.wait.aligned;" ::: "memory");
    }
}

typedef CUresult (*EncodeFn)(CUtensorMap*, CUtensorMapDataType, cuuint32_t, void*, const cuuint64_t*, const cuuint64_t*,
                             const cuuint32_t*, const cuuint32_t*, CUtensorMapInterleave, CUtensorMapSwizzle,
                             CUtensorMapL2promotion, CUtensorMapFloatOOBfill);

static void make_map(EncodeFn enc, CUtensorMap* m, CUtensorMapDataType dt, int rank, const void* base, const cuuint64_t* gd,
                     const cuuint64_t* gs, const cuuint32_t* bd, CUtensorMapSwizzle sw, CUtensorMapL2promotion prom) {
    cuuint32_t es[5] = {1, 1, 1, 1, 1};
    enc(m, dt, rank, const_cast<void*>(base), gd, gs, bd, es, CU_TENSOR_MAP_INTERLEAVE_NONE, sw,
        prom, CU_TENSOR_MAP_FLOAT_OOB_FILL_NONE);
}
static void make_map2(EncodeFn enc, CUtensorMap* m, const void* base, uint64_t cols, uint64_t rows, uint32_t bc, uint32_t br,
                      CUtensorMapL2promotion prom) {
    cuuint64_t gd[2] = {cols, rows};
    cuuint64_t gs[1] = {cols * 2};
    cuuint32_t bd[2] = {bc, br};
    make_map(enc, m, CU_TENSOR_MAP_DATA_TYPE_BFLOAT16, 2, base, gd, gs, bd, CU_TENSOR_MAP_SWIZZLE_128B, prom);
}

extern "C" void kernel_launch(void* const* d_in, const int* in_sizes, int n_in, void* d_out, int out_size) {
    (void)in_sizes; (void)n_in; (void)out_size;
    static EncodeFn enc = nullptr;
    if (!enc) {
        void* f = nullptr;
        cudaDriverEntryPointQueryResult q;
        cudaGetDriverEntryPoint("cuTensorMapEncodeTiled", &f, cudaEnableDefault, &q);
        enc = (EncodeFn)f;
        cudaFuncSetAttribute(gqa_fused_kernel, cudaFuncAttributeMaxDynamicSharedMemorySize, SM_TOTAL);
    }
    Params p;
    make_map2(enc, &p.x, d_in[0], 1024, 384, 64, 192, CU_TENSOR_MAP_L2_PROMOTION_L2_256B);
    make_map2(enc, &p.k, d_in[1], 128, 65536, 64, 128, CU_TENSOR_MAP_L2_PROMOTION_L2_128B);
    make_map2(enc, &p.v, d_in[2], 128, 65536, 64, 128, CU_TENSOR_MAP_L2_PROMOTION_L2_128B);
    make_map2(enc, &p.wq, d_in[3], 4096, 1024, 64, 64, CU_TENSOR_MAP_L2_PROMOTION_L2_128B);
    make_map2(enc, &p.wo, d_in[4], 1024, 4096, 64, 128, CU_TENSOR_MAP_L2_PROMOTION_L2_128B);
    {
        cuuint64_t gd[3] = {1024, 48, 8}, gs[2] = {2048, 98304};
        cuuint32_t bd[3] = {64, 16, 1};
        make_map(enc, &p.out, CU_TENSOR_MAP_DATA_TYPE_BFLOAT16, 3, d_out, gd, gs, bd, CU_TENSOR_MAP_SWIZZLE_128B,
                 CU_TENSOR_MAP_L2_PROMOTION_L2_256B);
    }
    p.xp = (const unsigned char*)d_in[0];
    p.wqp = (const unsigned char*)d_in[3];
    gqa_fused_kernel<<<NCTA, NTHREADS, SM_TOTAL, cudaStreamPerThread>>>(p, (__nv_bfloat16*)d_out);
}
```
